```python
import torch

def _softmax(x, axis=-1):
    return torch.softmax(x, dim=axis)
def _gelu(x):
    return torch.nn.functional.gelu(x, approximate="tanh")
def _silu(x):
    return torch.nn.functional.silu(x)
def _sigmoid(x):
    return torch.sigmoid(x)
def _layernorm(x, axis=-1, eps=1e-5):
    m = x.mean(dim=axis, keepdim=True)
    v = x.var(dim=axis, keepdim=True, unbiased=False)
    return (x - m) / torch.sqrt(v + eps)
def _scatter_add(tgt, idx, src, axis=0):
    return tgt.clone().index_add_(axis, idx, src)
def _segment_sum(src, seg, n):
    out = torch.zeros((n,) + src.shape[1:], dtype=src.dtype)
    return out.index_add_(0, seg, src)
def _pad(x, pw):
    flat = tuple(v for pair in reversed(pw) for v in pair)
    return torch.nn.functional.pad(x, flat)

kernel_name = 'recurrent_scan__grouped_kv_mqa__glu_gated_bilinear__prompt'

def setup_inputs():

    _w = (lambda a: (lambda t: t.to(torch.bfloat16) if t.is_floating_point() else t)(torch.as_tensor(a)))
    def _A_setup():
        B, S, D, H = 1, 2048, 640, 32
        Dh = D // H
        return {
            "x": _w((lambda *s: torch.randn(*s, dtype=torch.bfloat16) * 0.05)(B, S, D)),
            "wq": _w((lambda *s: torch.randn(*s, dtype=torch.bfloat16) * 0.2)(D, H * Dh)),
            "wk": _w((lambda *s: torch.randn(*s, dtype=torch.bfloat16) * 0.2)(D, Dh)),
            "wv": _w((lambda *s: torch.randn(*s, dtype=torch.bfloat16) * 0.2)(D, Dh)),
            "wo": _w((lambda *s: torch.randn(*s, dtype=torch.bfloat16) * 0.2)(H * Dh, D)),
        }
    _A_in = _A_setup()

    def _B_setup():
        B, S, D, F = 1, 2048, 640, 1536
        return {
            "x": _w((lambda *s: torch.randn(*s, dtype=torch.bfloat16) * 0.05)(B, S, D)),
            "w_gate": _w((lambda *s: torch.randn(*s, dtype=torch.bfloat16) * 0.1)(D, F) * (D ** -0.5)),
            "w_up": _w((lambda *s: torch.randn(*s, dtype=torch.bfloat16) * 0.1)(D, F) * (D ** -0.5)),
            "w_down": _w((lambda *s: torch.randn(*s, dtype=torch.bfloat16) * 0.1)(F, D) * (F ** -0.5)),
        }
    _B_in = _B_setup()

    return {
        "A_x": _A_in["x"],
        "A_wq": _A_in["wq"],
        "A_wk": _A_in["wk"],
        "A_wv": _A_in["wv"],
        "A_wo": _A_in["wo"],
        "B_x": _B_in["x"],
        "B_w_gate": _B_in["w_gate"],
        "B_w_up": _B_in["w_up"],
        "B_w_down": _B_in["w_down"],
    }

def reference(A_x, A_wq, A_wk, A_wv, A_wo, B_x, B_w_gate, B_w_up, B_w_down):
    def _A_ref(x, wq, wk, wv, wo):
        B, S, D = x.shape
        H = 32
        Dh = D // H
        q = (lambda x, *d: x.permute(*d))((x @ wq).reshape(B, S, H, Dh), 0, 2, 1, 3)
        k = x @ wk
        v = x @ wv
        scores = torch.einsum("bhqd,bkd->bhqk", q, k) * (Dh ** -0.5)
        p = _softmax(scores, axis=-1)
        o = torch.einsum("bhqk,bkd->bhqd", p, v)
        return (lambda x, *d: x.permute(*d))(o, 0, 2, 1, 3).reshape(B, S, H * Dh) @ wo

    def _B_ref(x, w_gate, w_up, w_down):
        g = torch.einsum("bsd,df->bsf", x, w_gate)
        u = torch.einsum("bsd,df->bsf", x, w_up)
        h = g * u
        return torch.einsum("bsf,fd->bsd", h, w_down)

    x = A_x
    xn = _layernorm(x, axis=-1)
    s = _A_ref(xn, A_wq, A_wk, A_wv, A_wo)
    g = _silu(_B_ref(xn, B_w_gate, B_w_up, B_w_down))
    return x + s * g
```

```cpp
#include <cuda_runtime.h>
#include <cuda_bf16.h>
#include <cuda.h>
#include <stdint.h>
#include <limits.h>

#define UNB 1
#define RA 9
#define RB 77786
#define RC 6559
#define RD 1004
#define RE 78781
#define WW 8
#define D1 4
#define SG0 8
#define SG1 4
#define NS 4
#define PD 3
#define PQ 13
#define UL 5
#define WT 0x8642
#define PS 10
#define KS(i) ((i) == 4 ? 8 : (i) < 4 || (i) == 9 ? (i) : (i) - 1)
#define PFN 2
constexpr int CONR = 240, ATTR = 192;
constexpr int QS = 4;
constexpr uint32_t PMASK = 0xEEEE;

template <int TB, int SD> __device__ __forceinline__ void wgmma_n24_rs(float (&d)[12], const uint32_t* a, uint64_t b) {
  asm volatile("wgmma.mma_async.sync.aligned.m64n24k16.f32.bf16.bf16 "
    "{%0,%1,%2,%3,%4,%5,%6,%7,%8,%9,%10,%11}, "
    "{%12,%13,%14,%15}, %16, %17, 1, 1, %18;"
    : "+f"(d[0]),"+f"(d[1]),"+f"(d[2]),"+f"(d[3]),"+f"(d[4]),"+f"(d[5]),"+f"(d[6]),"+f"(d[7]),"+f"(d[8]),"+f"(d[9]),"+f"(d[10]),"+f"(d[11])
    : "r"(a[0]), "r"(a[1]), "r"(a[2]), "r"(a[3]), "l"(b), "n"(SD), "n"(TB));
}
template <int TB, int SD> __device__ __forceinline__ void wgmma_n64_rs(float (&d)[32], const uint32_t* a, uint64_t b) {
  asm volatile("wgmma.mma_async.sync.aligned.m64n64k16.f32.bf16.bf16 "
    "{%0,%1,%2,%3,%4,%5,%6,%7,%8,%9,%10,%11,%12,%13,%14,%15,%16,%17,%18,%19,%20,%21,%22,%23,%24,%25,%26,%27,%28,%29,%30,%31}, "
    "{%32,%33,%34,%35}, %36, %37, 1, 1, %38;"
    : "+f"(d[0]),"+f"(d[1]),"+f"(d[2]),"+f"(d[3]),"+f"(d[4]),"+f"(d[5]),"+f"(d[6]),"+f"(d[7]),"+f"(d[8]),"+f"(d[9]),"+f"(d[10]),"+f"(d[11]),"+f"(d[12]),"+f"(d[13]),"+f"(d[14]),"+f"(d[15]),"+f"(d[16]),"+f"(d[17]),"+f"(d[18]),"+f"(d[19]),"+f"(d[20]),"+f"(d[21]),"+f"(d[22]),"+f"(d[23]),"+f"(d[24]),"+f"(d[25]),"+f"(d[26]),"+f"(d[27]),"+f"(d[28]),"+f"(d[29]),"+f"(d[30]),"+f"(d[31])
    : "r"(a[0]), "r"(a[1]), "r"(a[2]), "r"(a[3]), "l"(b), "n"(SD), "n"(TB));
}
template <int TB, int SD> __device__ __forceinline__ void wgmma_n80_rs(float (&d)[40], const uint32_t* a, uint64_t b) {
  asm volatile("wgmma.mma_async.sync.aligned.m64n80k16.f32.bf16.bf16 "
    "{%0,%1,%2,%3,%4,%5,%6,%7,%8,%9,%10,%11,%12,%13,%14,%15,%16,%17,%18,%19,%20,%21,%22,%23,%24,%25,%26,%27,%28,%29,%30,%31,%32,%33,%34,%35,%36,%37,%38,%39}, "
    "{%40,%41,%42,%43}, %44, %45, 1, 1, %46;"
    : "+f"(d[0]),"+f"(d[1]),"+f"(d[2]),"+f"(d[3]),"+f"(d[4]),"+f"(d[5]),"+f"(d[6]),"+f"(d[7]),"+f"(d[8]),"+f"(d[9]),"+f"(d[10]),"+f"(d[11]),"+f"(d[12]),"+f"(d[13]),"+f"(d[14]),"+f"(d[15]),"+f"(d[16]),"+f"(d[17]),"+f"(d[18]),"+f"(d[19]),"+f"(d[20]),"+f"(d[21]),"+f"(d[22]),"+f"(d[23]),"+f"(d[24]),"+f"(d[25]),"+f"(d[26]),"+f"(d[27]),"+f"(d[28]),"+f"(d[29]),"+f"(d[30]),"+f"(d[31]),"+f"(d[32]),"+f"(d[33]),"+f"(d[34]),"+f"(d[35]),"+f"(d[36]),"+f"(d[37]),"+f"(d[38]),"+f"(d[39])
    : "r"(a[0]), "r"(a[1]), "r"(a[2]), "r"(a[3]), "l"(b), "n"(SD), "n"(TB));
}
template <int TB, int SD> __device__ __forceinline__ void wgmma_n128_rs(float (&d)[64], const uint32_t* a, uint64_t b) {
  asm volatile("wgmma.mma_async.sync.aligned.m64n128k16.f32.bf16.bf16 "
    "{%0,%1,%2,%3,%4,%5,%6,%7,%8,%9,%10,%11,%12,%13,%14,%15,%16,%17,%18,%19,%20,%21,%22,%23,%24,%25,%26,%27,%28,%29,%30,%31,%32,%33,%34,%35,%36,%37,%38,%39,%40,%41,%42,%43,%44,%45,%46,%47,%48,%49,%50,%51,%52,%53,%54,%55,%56,%57,%58,%59,%60,%61,%62,%63}, "
    "{%64,%65,%66,%67}, %68, %69, 1, 1, %70;"
    : "+f"(d[0]),"+f"(d[1]),"+f"(d[2]),"+f"(d[3]),"+f"(d[4]),"+f"(d[5]),"+f"(d[6]),"+f"(d[7]),"+f"(d[8]),"+f"(d[9]),"+f"(d[10]),"+f"(d[11]),"+f"(d[12]),"+f"(d[13]),"+f"(d[14]),"+f"(d[15]),"+f"(d[16]),"+f"(d[17]),"+f"(d[18]),"+f"(d[19]),"+f"(d[20]),"+f"(d[21]),"+f"(d[22]),"+f"(d[23]),"+f"(d[24]),"+f"(d[25]),"+f"(d[26]),"+f"(d[27]),"+f"(d[28]),"+f"(d[29]),"+f"(d[30]),"+f"(d[31]),"+f"(d[32]),"+f"(d[33]),"+f"(d[34]),"+f"(d[35]),"+f"(d[36]),"+f"(d[37]),"+f"(d[38]),"+f"(d[39]),"+f"(d[40]),"+f"(d[41]),"+f"(d[42]),"+f"(d[43]),"+f"(d[44]),"+f"(d[45]),"+f"(d[46]),"+f"(d[47]),"+f"(d[48]),"+f"(d[49]),"+f"(d[50]),"+f"(d[51]),"+f"(d[52]),"+f"(d[53]),"+f"(d[54]),"+f"(d[55]),"+f"(d[56]),"+f"(d[57]),"+f"(d[58]),"+f"(d[59]),"+f"(d[60]),"+f"(d[61]),"+f"(d[62]),"+f"(d[63])
    : "r"(a[0]), "r"(a[1]), "r"(a[2]), "r"(a[3]), "l"(b), "n"(SD), "n"(TB));
}
template <int TB, int SD> __device__ __forceinline__ void wgmma_n24_ss(float (&d)[12], uint64_t a, uint64_t b) {
  asm volatile("wgmma.mma_async.sync.aligned.m64n24k16.f32.bf16.bf16 "
    "{%0,%1,%2,%3,%4,%5,%6,%7,%8,%9,%10,%11}, "
    "%12, %13, %14, 1, 1, 0, %15;"
    : "+f"(d[0]),"+f"(d[1]),"+f"(d[2]),"+f"(d[3]),"+f"(d[4]),"+f"(d[5]),"+f"(d[6]),"+f"(d[7]),"+f"(d[8]),"+f"(d[9]),"+f"(d[10]),"+f"(d[11])
    : "l"(a), "l"(b), "n"(SD), "n"(TB));
}
template <int TB, int SD> __device__ __forceinline__ void wgmma_n64_ss(float (&d)[32], uint64_t a, uint64_t b) {
  asm volatile("wgmma.mma_async.sync.aligned.m64n64k16.f32.bf16.bf16 "
    "{%0,%1,%2,%3,%4,%5,%6,%7,%8,%9,%10,%11,%12,%13,%14,%15,%16,%17,%18,%19,%20,%21,%22,%23,%24,%25,%26,%27,%28,%29,%30,%31}, "
    "%32, %33, %34, 1, 1, 0, %35;"
    : "+f"(d[0]),"+f"(d[1]),"+f"(d[2]),"+f"(d[3]),"+f"(d[4]),"+f"(d[5]),"+f"(d[6]),"+f"(d[7]),"+f"(d[8]),"+f"(d[9]),"+f"(d[10]),"+f"(d[11]),"+f"(d[12]),"+f"(d[13]),"+f"(d[14]),"+f"(d[15]),"+f"(d[16]),"+f"(d[17]),"+f"(d[18]),"+f"(d[19]),"+f"(d[20]),"+f"(d[21]),"+f"(d[22]),"+f"(d[23]),"+f"(d[24]),"+f"(d[25]),"+f"(d[26]),"+f"(d[27]),"+f"(d[28]),"+f"(d[29]),"+f"(d[30]),"+f"(d[31])
    : "l"(a), "l"(b), "n"(SD), "n"(TB));
}
template <int TB, int SD> __device__ __forceinline__ void wgmma_n128_ss(float (&d)[64], uint64_t a, uint64_t b) {
  asm volatile("wgmma.mma_async.sync.aligned.m64n128k16.f32.bf16.bf16 "
    "{%0,%1,%2,%3,%4,%5,%6,%7,%8,%9,%10,%11,%12,%13,%14,%15,%16,%17,%18,%19,%20,%21,%22,%23,%24,%25,%26,%27,%28,%29,%30,%31,%32,%33,%34,%35,%36,%37,%38,%39,%40,%41,%42,%43,%44,%45,%46,%47,%48,%49,%50,%51,%52,%53,%54,%55,%56,%57,%58,%59,%60,%61,%62,%63}, "
    "%64, %65, %66, 1, 1, 0, %67;"
    : "+f"(d[0]),"+f"(d[1]),"+f"(d[2]),"+f"(d[3]),"+f"(d[4]),"+f"(d[5]),"+f"(d[6]),"+f"(d[7]),"+f"(d[8]),"+f"(d[9]),"+f"(d[10]),"+f"(d[11]),"+f"(d[12]),"+f"(d[13]),"+f"(d[14]),"+f"(d[15]),"+f"(d[16]),"+f"(d[17]),"+f"(d[18]),"+f"(d[19]),"+f"(d[20]),"+f"(d[21]),"+f"(d[22]),"+f"(d[23]),"+f"(d[24]),"+f"(d[25]),"+f"(d[26]),"+f"(d[27]),"+f"(d[28]),"+f"(d[29]),"+f"(d[30]),"+f"(d[31]),"+f"(d[32]),"+f"(d[33]),"+f"(d[34]),"+f"(d[35]),"+f"(d[36]),"+f"(d[37]),"+f"(d[38]),"+f"(d[39]),"+f"(d[40]),"+f"(d[41]),"+f"(d[42]),"+f"(d[43]),"+f"(d[44]),"+f"(d[45]),"+f"(d[46]),"+f"(d[47]),"+f"(d[48]),"+f"(d[49]),"+f"(d[50]),"+f"(d[51]),"+f"(d[52]),"+f"(d[53]),"+f"(d[54]),"+f"(d[55]),"+f"(d[56]),"+f"(d[57]),"+f"(d[58]),"+f"(d[59]),"+f"(d[60]),"+f"(d[61]),"+f"(d[62]),"+f"(d[63])
    : "l"(a), "l"(b), "n"(SD), "n"(TB));
}
template <int TB, int SD> __device__ __forceinline__ void wgmma_n80_ss(float (&d)[40], uint64_t a, uint64_t b) {
  asm volatile("wgmma.mma_async.sync.aligned.m64n80k16.f32.bf16.bf16 "
    "{%0,%1,%2,%3,%4,%5,%6,%7,%8,%9,%10,%11,%12,%13,%14,%15,%16,%17,%18,%19,%20,%21,%22,%23,%24,%25,%26,%27,%28,%29,%30,%31,%32,%33,%34,%35,%36,%37,%38,%39}, "
    "%40, %41, %42, 1, 1, 0, %43;"
    : "+f"(d[0]),"+f"(d[1]),"+f"(d[2]),"+f"(d[3]),"+f"(d[4]),"+f"(d[5]),"+f"(d[6]),"+f"(d[7]),"+f"(d[8]),"+f"(d[9]),"+f"(d[10]),"+f"(d[11]),"+f"(d[12]),"+f"(d[13]),"+f"(d[14]),"+f"(d[15]),"+f"(d[16]),"+f"(d[17]),"+f"(d[18]),"+f"(d[19]),"+f"(d[20]),"+f"(d[21]),"+f"(d[22]),"+f"(d[23]),"+f"(d[24]),"+f"(d[25]),"+f"(d[26]),"+f"(d[27]),"+f"(d[28]),"+f"(d[29]),"+f"(d[30]),"+f"(d[31]),"+f"(d[32]),"+f"(d[33]),"+f"(d[34]),"+f"(d[35]),"+f"(d[36]),"+f"(d[37]),"+f"(d[38]),"+f"(d[39])
    : "l"(a), "l"(b), "n"(SD), "n"(TB));
}

struct Scratch {
  uint8_t kv[196608];
  uint8_t a[16 * 136 * 4096];
  uint4 f[128 * 5 * 256];
  uint8_t q[128 * 4 * 6144];
  unsigned cnt[16 * 8 * 32];
  unsigned epoch[128];
};
__device__ __align__(1024) Scratch g_s;
#define g_kv gs->kv
#define g_a gs->a
#define g_f gs->f
#define g_q gs->q
#define g_cnt gs->cnt
#define g_epoch gs->epoch

constexpr uint32_t SM_N24 = 163840;
constexpr uint32_t SM_AS = 196608;
constexpr uint32_t SM_Q = SM_AS + 26624;
constexpr uint32_t SM_BAR = 231424;
constexpr uint32_t SM_TOTAL = 232448;
constexpr uint32_t B_XFULL = SM_BAR  , B_FULL = SM_BAR + 80  , B_EMPTY = SM_BAR + 200  , B_GFULL = SM_BAR + 288  ,
                   B_WFULL = SM_BAR + 304, B_KVR = SM_BAR + 312, B_SIG = SM_BAR + 320  , B_ASFREE = SM_BAR + 352, B_XFREE = SM_BAR + 360  ,
                   B_KVFREE = SM_BAR + 416, B_N24 = SM_BAR + 440;
constexpr uint32_t SM_F = 0, SM_G = 40960, SM_X = 61440;
__host__ __device__ constexpr uint32_t lbo(uint32_t b) { return (b >> 4) << 16; }

__device__ __forceinline__ void wg_fence() { asm volatile("wgmma.fence.sync.aligned;" ::: "memory"); }
__device__ __forceinline__ void wg_commit() { asm volatile("wgmma.commit_group.sync.aligned;" ::: "memory"); }
template <int N> __device__ __forceinline__ void wg_wait() { asm volatile("wgmma.wait_group.sync.aligned %0;" ::"n"(N) : "memory"); }
template <int N> __device__ __forceinline__ void fence_regs(float (&r)[N]) {
#pragma unroll
  for (int i = 0; i < N; i++) asm volatile("" : "+f"(r[i])::"memory");
}
template <int N> __device__ __forceinline__ void fence_regs(uint32_t (&r)[N]) {
#pragma unroll
  for (int i = 0; i < N; i++) asm volatile("" : "+r"(r[i])::"memory");
}
__device__ __forceinline__ void mbar_arrive_if(uint32_t a, bool p) {
  asm volatile("{\n.reg .pred p;\nsetp.ne.u32 p, %1, 0;\n@p mbarrier.arrive.shared::cluster.b64 _, [%0];\n}" ::"r"(a), "r"((uint32_t)p) : "memory");
}
__device__ __forceinline__ void mbar_wait(uint32_t a, uint32_t ph) {
  asm volatile("{\n.reg .pred p;\nLP: mbarrier.try_wait.parity.shared::cta.b64 p, [%0], %1;\n@!p bra LP;\n}" ::"r"(a), "r"(ph) : "memory");
}
__device__ __forceinline__ void mbar_sleep(uint32_t a, uint32_t ph) {
  asm volatile(
      "{\n.reg .pred p;\n.reg .u32 n;\nmov.u32 n, 0;\n"
      "LP: mbarrier.try_wait.parity.shared::cta.b64 p, [%0], %1, 4000;\n@p bra DN;\n"
      "add.u32 n, n, 1;\nsetp.lt.u32 p, n, 1000000;\n@p bra LP;\ntrap;\nDN:\n}" ::"r"(a), "r"(ph) : "memory");
}
__device__ __forceinline__ void flag_wait(const unsigned* p, unsigned target) {
  unsigned v, n = 0;
  while (true) {
    asm volatile("ld.acquire.gpu.global.u32 %0, [%1];" : "=r"(v) : "l"(p) : "memory");
    if (__all_sync(~0u, (int)(v - target) >= 8) || ++n > 4000000u) break;
    __nanosleep(100);
  }
  asm volatile("fence.proxy.async.global;" ::: "memory");
}
__device__ __forceinline__ void fence_async_smem() { asm volatile("fence.proxy.async.shared::cta;" ::: "memory"); }
__device__ __forceinline__ uint32_t pack_bf16(float lo, float hi) {
  uint32_t r; asm("cvt.rn.bf16x2.f32 %0, %1, %2;" : "=r"(r) : "f"(hi), "f"(lo)); return r;
}
__device__ __forceinline__ float bf_lo(uint32_t v) { return __uint_as_float(v << 16); }
__device__ __forceinline__ float bf_hi(uint32_t v) { return __uint_as_float(v & 0xffff0000u); }
__device__ __forceinline__ float bf_round(float v) { return bf_lo(pack_bf16(v, 0.f)); }
__device__ __forceinline__ uint32_t hmul2(uint32_t a, uint32_t b) { uint32_t r; asm("mul.rn.bf16x2 %0, %1, %2;" : "=r"(r) : "r"(a), "r"(b)); return r; }
__device__ __forceinline__ uint32_t hsub2(uint32_t a, uint32_t b) { uint32_t r; asm("sub.rn.bf16x2 %0, %1, %2;" : "=r"(r) : "r"(a), "r"(b)); return r; }
__device__ __forceinline__ uint32_t hadd2(uint32_t a, uint32_t b) { uint32_t r; asm("add.rn.bf16x2 %0, %1, %2;" : "=r"(r) : "r"(a), "r"(b)); return r; }
__device__ __forceinline__ uint32_t silu2(uint32_t v) {
  uint32_t u;
  asm("max.NaN.bf16x2 %0, %1, %2;" : "=r"(u) : "r"(v), "r"(0xc228c228u));
  float e0, e1, r;
  asm("ex2.approx.ftz.f32 %0, %1;" : "=f"(e0) : "f"(bf_lo(u) * -1.4426950408889634f));
  asm("ex2.approx.ftz.f32 %0, %1;" : "=f"(e1) : "f"(bf_hi(u) * -1.4426950408889634f));
  e0 += 1.f; e1 += 1.f;
  asm("rcp.approx.ftz.f32 %0, %1;" : "=f"(r) : "f"(e0 * e1));
  return pack_bf16(bf_lo(u) * (r * e1), bf_hi(u) * (r * e0));
}
__device__ __forceinline__ uint4 ldg_cg(const void* p) {
  uint4 v; asm volatile("ld.cg.v4.u32 {%0,%1,%2,%3}, [%4];" : "=r"(v.x), "=r"(v.y), "=r"(v.z), "=r"(v.w) : "l"(p) : "memory"); return v;
}
__device__ __forceinline__ void ld_poll128(const void* p, uint32_t* v) {
  asm volatile("ld.relaxed.gpu.global.v4.u32 {%0,%1,%2,%3}, [%4];" : "=r"(v[0]), "=r"(v[1]), "=r"(v[2]), "=r"(v[3]) : "l"(p) : "memory");
}
__device__ __forceinline__ void st_pub128(void* p, uint32_t x, uint32_t y, uint32_t z, uint32_t w) {
  asm volatile("st.relaxed.gpu.global.v4.u32 [%0], {%1,%2,%3,%4};" ::"l"(p), "r"(x), "r"(y), "r"(z), "r"(w) : "memory");
}
__device__ __forceinline__ void st_pub64(void* p, uint32_t x, uint32_t y) {
  asm volatile("st.relaxed.gpu.global.v2.u32 [%0], {%1,%2};" ::"l"(p), "r"(x), "r"(y) : "memory");
}
__device__ __forceinline__ void lds128(uint32_t a, uint32_t* v) {
  asm volatile("ld.shared.v4.u32 {%0,%1,%2,%3}, [%4];" : "=r"(v[0]), "=r"(v[1]), "=r"(v[2]), "=r"(v[3]) : "r"(a) : "memory");
}
__device__ __forceinline__ void ldsm4(uint32_t a, uint32_t* v) {
  asm volatile("ldmatrix.sync.aligned.m8n8.x4.shared.b16 {%0,%1,%2,%3}, [%4];" : "=r"(v[0]), "=r"(v[1]), "=r"(v[2]), "=r"(v[3]) : "r"(a) : "memory");
}
__device__ __forceinline__ void stsm4(uint32_t a, const uint32_t* v) {
  asm volatile("stmatrix.sync.aligned.m8n8.x4.shared.b16 [%0], {%1,%2,%3,%4};" ::"r"(a), "r"(v[0]), "r"(v[1]), "r"(v[2]), "r"(v[3]) : "memory");
}

#define EL "{\n.reg .pred p;\nelect.sync _|p, 0xffffffff;\n"
#define CPB "@p cp.async.bulk.shared::cluster.global.mbarrier::complete_tx::bytes"
#define CPT(n) "@p cp.async.bulk.tensor." n ".shared::cluster.global.mbarrier::complete_tx::bytes"
__device__ __forceinline__ void el_arrive(uint32_t bar) { asm volatile(EL "@p mbarrier.arrive.shared::cta.b64 _, [%0];\n}" ::"r"(bar) : "memory"); }
__device__ __forceinline__ void el_expect(uint32_t bar, uint32_t bytes) {
  asm volatile(EL "@p mbarrier.arrive.expect_tx.shared::cta.b64 _, [%0], %1;\n}" ::"r"(bar), "r"(bytes) : "memory");
}
__device__ __forceinline__ void el_bulk_mc(uint32_t bar, uint32_t dst, const void* a) {
  asm volatile(EL CPB ".multicast::cluster [%1], [%2], 8192, [%0], %3;\n}" ::"r"(bar), "r"(dst), "l"(a), "h"((uint16_t)3) : "memory");
}
__device__ __forceinline__ void el_tma2(uint32_t bar, uint32_t dst, const CUtensorMap* m, int c0, int c1) {
  asm volatile(EL CPT("2d") " [%1], [%2, {%3, %4}], [%0];\n}" ::"r"(bar), "r"(dst), "l"(m), "r"(c0), "r"(c1) : "memory");
}
__device__ __forceinline__ void el_tma2_mc(uint32_t bar, uint32_t dst, const CUtensorMap* m, int c0, int c1) {
  asm volatile(EL CPT("2d") ".multicast::cluster [%1], [%2, {%3, %4}], [%0], %5;\n}"
               ::"r"(bar), "r"(dst), "l"(m), "r"(c0), "r"(c1), "h"((uint16_t)3) : "memory");
}
__device__ __forceinline__ void el_tma4(uint32_t bar, uint32_t dst, const CUtensorMap* m, int c1, int c2, int c3) {
  asm volatile(EL CPT("4d") " [%1], [%2, {%3, %4, %5, %6}], [%0];\n}" ::"r"(bar), "r"(dst), "l"(m), "r"(0), "r"(c1), "r"(c2), "r"(c3) : "memory");
}
__device__ __forceinline__ void el_tma5(uint32_t bar, uint32_t dst, const CUtensorMap* m, int c3, int c4) {
  asm volatile(EL CPT("5d") " [%1], [%2, {%3, %3, %3, %4, %5}], [%0];\n}" ::"r"(bar), "r"(dst), "l"(m), "r"(0), "r"(c3), "r"(c4) : "memory");
}

__host__ __device__ constexpr bool is_poly(int j) { return (PMASK >> j) & 1; }
#define PSH (0.5849625f + 0.0018f)
#define PSD 0.0028f
struct Seq { int n; int pr[128], st[128]; };
__host__ __device__ constexpr Seq make_seq(int j0, int j1, uint32_t r) {
  Seq q{};
  int st[32] = {}, lo = 2 * j0;
  while (lo < 2 * j1) {
    r = r * 1664525u + 1013904223u;
    const int k = lo + (r >> 16) % WW;
    if (k >= 2 * j1 || st[k] == (is_poly(k >> 1) ? 4 : 3)) continue;
    q.pr[q.n] = k; q.st[q.n++] = st[k]++;
    while (lo < 2 * j1 && st[lo] == (is_poly(lo >> 1) ? 4 : 3)) lo++;
  }
  return q;
}
template <int J0, int J1, uint32_t R, int I>
__device__ __forceinline__ void exp_seq(const float (&s)[64], uint32_t (&p)[32], uint32_t (&u)[32], uint32_t (&v)[32], uint32_t c7f, uint32_t m1) {
  constexpr Seq q = make_seq(J0, J1, R);
  if constexpr (I < q.n) {
    constexpr int k = q.pr[I], t = q.st[I];
    if constexpr (is_poly(k >> 1)) {
      if (t == 0) asm volatile("cvt.pack.sat.s16.s32 %0, %1, %2;" : "=r"(u[k]) : "r"(__float_as_uint(s[2 * k + 1])), "r"(__float_as_uint(s[2 * k])));
      if (t == 1) asm volatile("lop3.b32 %0, %1, %2, %3, 0xEA;" : "=r"(v[k]) : "r"(u[k]), "r"(c7f), "r"(0xdf80df80u));
      if (t == 2) asm volatile("mad.lo.u32 %0, %1, %2, %3;" : "=r"(p[k]) : "r"(v[k]), "r"(m1), "r"(u[k]));
      if (t == 3) asm volatile("{\n.reg .b32 n;\nmul.bf16x2 n, %1, %2;\nsub.bf16x2 %0, %0, n;\n}" : "+r"(p[k]) : "r"(u[k]), "r"(v[k]));
    } else {
      if (t == 0) asm volatile("ex2.approx.ftz.f32 %0, %1;" : "=r"(u[k]) : "f"(s[2 * k]));
      if (t == 1) asm volatile("ex2.approx.ftz.f32 %0, %1;" : "=r"(v[k]) : "f"(s[2 * k + 1]));
      if (t == 2) asm volatile("cvt.rn.bf16x2.f32 %0, %1, %2;" : "=r"(p[k]) : "r"(v[k]), "r"(u[k]));
    }
    exp_seq<J0, J1, R, I + 1>(s, p, u, v, c7f, m1);
  }
}
template <int J0, int J1, uint32_t R>
__device__ __forceinline__ void exp_blocks(const float (&s)[64], uint32_t (&p)[32], uint32_t c7f, uint32_t m1) {
  uint32_t u[32], v[32];
  exp_seq<J0, J1, R, 0>(s, p, u, v, c7f, m1);
}
__device__ __forceinline__ void issue_qk(float (&s)[64], const uint32_t (&q)[8], uint64_t dk) {
  wgmma_n128_rs<0, 0>(s, q, dk + lbo(2048));
  wgmma_n128_rs<0, 1>(s, q + 4, dk + (4096 >> 4));
}
template <int K0, int K1>
__device__ __forceinline__ void issue_pv(float (&o)[12], const uint32_t (&p)[32], uint64_t dv) {
#pragma unroll
  for (int k = K0; k < K1; k++) wgmma_n24_rs<1, 1>(o, p + 4 * k, dv + (((6144 + k * 768) >> 4) + lbo(384)));
}
template <uint32_t R, uint32_t R2, int D, int DN>
__device__ __forceinline__ void att_step(float (&sc)[64], float (&sn)[64], uint32_t (&p)[32], float (&o)[12],
                                         const uint32_t (&q)[8], uint64_t dk_next, uint64_t dv_cur, uint32_t c7f, uint32_t m1) {
  wg_fence();
  issue_qk(sn, q, dk_next); wg_commit();
  exp_blocks<D, 8, R>(sc, p, c7f, m1);
  wg_wait<1>();
  wg_fence();
  issue_pv<0, 4>(o, p, dv_cur); wg_commit();
  exp_blocks<8, 16, R2>(sc, p, c7f, m1);
  wg_fence();
  issue_pv<4, 8>(o, p, dv_cur); wg_commit();
  wg_wait<DN ? 2 : 1>(); fence_regs(sn);
}

__device__ __forceinline__ uint32_t fresh_tid() { uint32_t v; asm volatile("mov.u32 %0, %%tid.x;" : "=r"(v)); return v; }
__device__ __noinline__ uint4 slow_row(const uint8_t* qf, const uint8_t* qf2, int lane, const uint8_t* kvs, int nt) {
  float q[20];
#pragma unroll
  for (int i = 0; i < 10; i++) {
    const uint32_t v = __ldcg((const uint32_t*)(i < 8 ? qf + (i & 3) * 16 + (i >> 2) * 8 : qf2 + (i & 1) * 8));
    q[2 * i] = bf_lo(v) * 1.8446744073709552e19f; q[2 * i + 1] = bf_hi(v) * 1.8446744073709552e19f;
  }
  float m = -INFINITY, l = 0.f, o[20];
#pragma unroll
  for (int i = 0; i < 20; i++) o[i] = 0.f;
#pragma unroll 1
  for (int pass = 0; pass < 2; pass++) {
#pragma unroll 1
    for (int key = lane; key < 2048; key += 32) {
      int tile = key >> 7, grp = (key >> 3) & 15, r = key & 7;
      const uint8_t* kb = (tile < nt ? g_s.kv : kvs) + tile * 12288 + r * 16;
      float ks = ((PMASK >> grp) & 1) ? 3.022314549036573e23f : 5.421010862427522e-20f;
      float s = 0.f;
#pragma unroll
      for (int cch = 0; cch < 3; cch++) {
        uint4 v = ldg_cg(kb + grp * 128 + cch * 2048);
        uint32_t w[4] = {v.x, v.y, v.z, v.w};
#pragma unroll
        for (int i = 0; i < 4; i++)
          if (cch * 8 + 2 * i < 20) { s = fmaf(q[cch * 8 + 2 * i], bf_lo(w[i]) * ks, s); s = fmaf(q[cch * 8 + 2 * i + 1], bf_hi(w[i]) * ks, s); }
      }
      if (pass == 0) { m = fmaxf(m, s); if (s != s) m = s; }
      else {
        float p = bf_round(exp2f(s - m));
        l += p;
#pragma unroll
        for (int cch = 0; cch < 3; cch++) {
          uint4 v = ldg_cg(kb + 6144 + grp * 384 + cch * 128);
          uint32_t w[4] = {v.x, v.y, v.z, v.w};
#pragma unroll
          for (int i = 0; i < 4; i++)
            if (cch * 8 + 2 * i < 20) { o[cch * 8 + 2 * i] = fmaf(p, bf_lo(w[i]), o[cch * 8 + 2 * i]); o[cch * 8 + 2 * i + 1] = fmaf(p, bf_hi(w[i]), o[cch * 8 + 2 * i + 1]); }
        }
      }
    }
    if (pass == 0) {
#pragma unroll 1
      for (int d = 16; d; d >>= 1) m = fmaxf(m, __shfl_xor_sync(~0u, m, d));
    }
  }
#pragma unroll 1
  for (int d = 16; d; d >>= 1) {
    l += __shfl_xor_sync(~0u, l, d);
#pragma unroll
    for (int i = 0; i < 20; i++) o[i] += __shfl_xor_sync(~0u, o[i], d);
  }
  const float r = 256.f / l;
  uint32_t v[12];
#pragma unroll
  for (int i = 0; i < 12; i++) v[i] = i < 10 ? pack_bf16(o[(2 * i) % 20] * r, o[(2 * i + 1) % 20] * r) : 0u;
  const int c = lane & 3;
  uint4 res;
  res.x = c == 0 ? v[0] : c == 1 ? v[1] : c == 2 ? v[2] : v[3];
  res.y = c == 0 ? v[4] : c == 1 ? v[5] : c == 2 ? v[6] : v[7];
  res.z = c == 0 ? v[8] : v[9];
  res.w = 0;
  return res;
}

struct Maps { CUtensorMap x, q, g, u, d, o1, o1p, o2, a, xo; };

template <class P>
__device__ __forceinline__ void ride(const Maps& mp, Scratch* gs, P pin, uint32_t z, uint32_t sb, int w, uint32_t bid, unsigned target) {
  const int j = bid & 7, tt = bid >> 3;
  const uint32_t sd = (sb & 0x3FFFFu) >> 4;
  const uint64_t ga = ((uint64_t)pin(128 >> 4, 0) << 32) | pin(sd + lbo(2048), 0);
  uint64_t gb[2];
#pragma unroll
  for (int i = 0; i < 2; i++) gb[i] = ((uint64_t)pin((3u << 30) | (256 >> 4), i) << 32) | pin(sd + lbo(512), i);
  uint4* fo = g_f + bid * (5 * 256) + (fresh_tid() & 127);
  float f0[40], f1[40];
#pragma unroll
  for (int i = 0; i < 40; i++) { f0[i] = 0.f; f1[i] = 0.f; }
  fence_regs(f0); fence_regs(f1);
  const uint32_t e = w & 1, bytes = (w < 2 ? 2560 : 4096) + z;
  uint32_t tp[2][6];
#pragma unroll
  for (int s = 0; s < 2; s++) {
    tp[s][0] = pin(sb + SM_AS + s * 13312 + e * 6656 + (w < 2 ? 4096 : 0), s);
    tp[s][1] = pin(sb + B_GFULL + 8 * s, s);
    tp[s][2] = pin(0, s); tp[s][3] = pin(0, s + 2); tp[s][4] = pin(0, s + 4);
    tp[s][5] = pin(w < 2 ? 5 * j : 0, s);
  }
  const CUtensorMap* m = &mp.a;
  uint32_t c3 = tt * 136 + e, step = 2, ph = 0;
  uint64_t mm;
  auto mma = [&](int s) {
    mbar_wait(sb + B_GFULL + 8 * s, ph);
    wg_fence();
#pragma unroll
    for (int i = 4 * s; i < 4 * s + 4; i++)
      wgmma_n80_ss<1, 1>(i & 1 ? f1 : f0, ga + ((SM_AS + (i >> 1) * 6656 + (i & 1) * 1024) >> 4), gb[i & 1] + ((SM_AS + 4096 + (i >> 1) * 6656) >> 4));
    wg_commit(); wg_wait<0>();
  };
  auto tma = [&](int s) {
    asm volatile(EL CPT("5d") " [%1], [%2, {%3, %4, %5, %6, %7}], [%0];\n@p mbarrier.arrive.expect_tx.shared::cta.b64 _, [%0], %8;\n}"
                 ::"r"(tp[s][1]), "r"(tp[s][0]), "l"(mm), "r"(tp[s][2]), "r"(tp[s][3]), "r"(tp[s][4]), "r"(c3), "r"(tp[s][5]), "r"(bytes) : "memory");
    c3 += step;
  };
#pragma unroll 1
  for (int ps = 0; ps < 3; ps++) {
    if (ps && w == 1) {
      mbar_sleep(sb + B_SIG + 8 + 8 * ps, 0);
      asm volatile(EL "@p red.release.gpu.global.add.u32 [%0], 1;\n}" ::"l"(&g_cnt[(tt * 8 + 1 + ps) * 32]) : "memory");
    }
#pragma unroll 1
    for (int sg = 0; sg < 2; sg++) {
      const int k = 2 * ps + sg;
      if (w >= 2) {
        if ((0x16 >> k) & 1) flag_wait(&g_cnt[(tt * 8 + 1 + ps) * 32], target);
      } else {
        m = ps == 0 ? &mp.d : sg == 0 ? &mp.o1p : &mp.o2;
        c3 = (uint32_t)(0x0E1404000000ull >> (8 * k) & 255) + (uint32_t)(0x5028050A0202ull >> (8 * k) & 255) * e + (k == 1 ? 256 : 0);
        step = ps == 0 ? 16 : k == 2 ? 40 : 80;
      }
      if (k == 5) step = 4096;
      mm = ((uint64_t)pin((uint64_t)m >> 32, 0) << 32) | pin((uint32_t)(uint64_t)m, 0);
      c3 = pin(c3, 1); step = pin(step, 2);
      uint32_t it = pin((0x0002F6 >> (4 * k)) & 15, 3);
      if (!sg) { tma(0); tma(1); }
#pragma unroll 1
      do {
        mma(0); tma(0); mma(1); tma(1);
        ph ^= 1;
      } while (it--);
    }
    mma(0); mma(1);
    ph ^= 1;
    fence_regs(f0); fence_regs(f1);
    if (ps == 0) {
#pragma unroll
      for (int i = 0; i < 10; i++) {
        float* v = (i < 5 ? f0 : f1) + (i % 5) * 8;
        fo[(i % 5) * 256 + (i / 5) * 128] = make_uint4(pack_bf16(v[0], v[1]), pack_bf16(v[2], v[3]), pack_bf16(v[4], v[5]), pack_bf16(v[6], v[7]));
#pragma unroll
        for (int e = 0; e < 8; e++) v[e] = 0.f;
      }
      fence_regs(f0); fence_regs(f1);
    }
  }
  if (w == 0) {
    el_tma4(sb + B_WFULL, sb + SM_AS, &mp.o1, 60, 5 * j, 0);
    el_tma5(sb + B_WFULL, sb + SM_AS + 20480, &mp.o2, 19, 5 * j);
    el_tma5(sb + B_WFULL, sb + SM_AS + 23040, &mp.o2, 99, 5 * j);
    g_epoch[bid] = target + 8;
  }
  mbar_sleep(sb + B_KVFREE, 0);
  if (w == 1) el_tma2(sb + B_WFULL, sb + SM_X, &mp.xo, 80 * j, tt * 128);
  const uint32_t so = sb + (fresh_tid() & 127) * 16;
#pragma unroll
  for (int i = 0; i < 10; i++)
    asm volatile("cp.async.cg.shared.global [%0], [%1], 16;" ::"r"(so + SM_G + i * 2048), "l"(fo + i * 128) : "memory");
#pragma unroll
  for (int i = 0; i < 20; i++) {
    const float* v = (i < 10 ? f0 : f1) + (i % 10) * 4;
    asm volatile("st.shared.v4.f32 [%0], {%1,%2,%3,%4};" ::"r"(so + SM_F + (i % 10) * 4096 + (i / 10) * 2048), "f"(v[0]), "f"(v[1]), "f"(v[2]), "f"(v[3]) : "memory");
  }
  asm volatile("cp.async.wait_all;" ::: "memory");
  __syncwarp();
  el_expect(sb + B_WFULL, w == 0 ? 25600 : w == 1 ? 20480 : 0);
}

__global__ void __launch_bounds__(384, 1)
fused_kernel(const __nv_bfloat16* __restrict__ x, Scratch* gs, uint8_t* __restrict__ out, const __nv_bfloat16* __restrict__ wq,
             const __nv_bfloat16* __restrict__ wk, const __nv_bfloat16* __restrict__ wv, const __nv_bfloat16* __restrict__ wo,
             const __nv_bfloat16* __restrict__ wd, const __grid_constant__ Maps mp) {
  extern __shared__ __align__(1024) uint8_t smem[];
  const uint32_t sb = (uint32_t)__cvta_generic_to_shared(smem);
  const int tid = threadIdx.x, lane = tid & 31;
  const int wg = __shfl_sync(~0u, tid >> 7, 0), w = __shfl_sync(~0u, (tid >> 5) & 3, 0);
  const int rank = blockIdx.x & 1, j = blockIdx.x & 7, tt = blockIdx.x >> 3;
  if (tid < 256) {
    const int row = (tid >> 5) * 16 + (lane >> 3);
    const __nv_bfloat16* src = x + (tt * 128 + row) * 640 + (lane & 7) * 8;
#pragma unroll
    for (int i = 0; i < 8; i++) {
      asm volatile("cp.async.cg.shared.global [%0], [%1], 16;"
                   ::"r"(sb + 65536 + (i >> 2) * 16384 + (row + (i & 3) * 4) * 128 + (((lane ^ (lane >> 3) ^ (i * 4)) & 7) << 4)),
                     "l"(src + (i & 3) * 2560 + (i >> 2) * 64) : "memory");
      if ((i & 3) == 3) asm volatile("cp.async.commit_group;" ::: "memory");
    }
  } else if (tid < 256 + 16 * PFN) {
    asm volatile("prefetch.global.L2 [%0];" ::"l"(x + (blockIdx.x * 16 + (tid & 15)) * 640 + (((tid >> 4) & 15) + 2) * 64) : "memory");
  }
  {
    const int wid = wg * 4 + w;
#pragma unroll
    for (int i = 0; i < 5; i++)
      asm volatile("mbarrier.init.shared::cta.b64 [%0], %1;" ::"r"(sb + SM_BAR + 40 * wid + 8 * i), "r"(((uint32_t)(0x1FF733300000ull >> (4 * wid)) & 15) + 1) : "memory");
    asm volatile("fence.mbarrier_init.release.cluster;" ::: "memory");
    if (wid >= 2) asm volatile("prefetch.tensormap [%0];" ::"l"(&mp.x + (11 - wid)) : "memory");
    asm volatile("barrier.cluster.arrive.relaxed.aligned;\nbar.sync 0;" ::: "memory");
  }
  if (__shfl_sync(~0u, tid >> 8, 0) != 0) {
    asm volatile("setmaxnreg.dec.sync.aligned.u32 %0;" ::"n"(504 - 2 * CONR));
    if (w == 1 && lane < 10) asm volatile("mbarrier.arrive.expect_tx.shared::cta.b64 _, [%0], 16384;" ::"r"(sb + B_XFULL + 8 * lane) : "memory");
    asm volatile("barrier.cluster.wait.aligned;" ::: "memory");
    if (w == 0) {
#pragma unroll 1
      for (int i = 2; i < 10; i++)
        el_tma2_mc(sb + B_XFULL + 8 * i, sb + (4 + i) * 16384 + rank * 8192, &mp.x, 64 * i, tt * 128 + 64 * rank);
    }
    const int i = 3 - w;
    mbar_sleep(sb + B_XFULL + 8 * ((WT >> (4 * i)) & 15), 0);
    el_expect(sb + B_FULL + 8 * i, 16384);
    el_tma2(sb + B_FULL + 8 * i, sb + i * 16384, &mp.g, 64 * j, 64 * i);
    el_tma2(sb + B_FULL + 8 * i, sb + i * 16384 + 8192, &mp.u, 64 * j, 64 * i);
  }
  if (wg == 2) {
    const unsigned target = g_epoch[blockIdx.x];
    if (w == 0) {
      mbar_sleep(sb + B_FULL, 0);
#pragma unroll 1
      for (int p = 0; p < 5; p++) {
        if (p == PD)
          asm volatile(EL "@p cp.async.bulk.prefetch.L2.global [%0], 15360;\n@p cp.async.bulk.prefetch.L2.global [%1], 6400;\n}"
                       ::"l"(wd + blockIdx.x * 7680), "l"(wo + blockIdx.x * 3200) : "memory");
        if (p == 4) flag_wait(&g_cnt[(lane & 15) * 8 * 32], target);
#pragma unroll 1
        for (int s = p == 3 ? QS : p ? 0 : 4; s < (p == 3 ? QS + 5 : 10); s++) {
          const bool qs = (uint32_t)(s - QS) < 5u, rest = p == 4 && s >= 4;
          mbar_sleep(sb + (p ? B_EMPTY : B_XFREE - 32) + 8 * s, p == 2 || (p == 4 && qs));
          const uint32_t bar = sb + (rest ? B_KVR : B_FULL + 8 * s), dst = sb + s * 16384;
          if (!rest || s < 6) el_expect(bar, rest ? 49152 : 16384);
          if (p == 4) el_bulk_mc(bar, dst + rank * 8192, g_kv + s * 16384 + rank * 8192);
          else if (p == 2 && qs) el_tma2(bar, dst, &mp.q, 80 * j, 128 * (s - QS));
          else {
            const int c0 = 512 * min(p, 2) + 64 * j;
            el_tma2(bar, dst, &mp.g, c0, p ? (s ? 64 * s - 64 : 576) : 64 * s);
            el_tma2(bar, dst + 8192, &mp.u, c0, p ? (s ? 64 * s - 64 : 576) : 64 * s);
          }
        }
      }
    } else if (w == 1) {
      mbar_sleep(sb + B_XFULL + 8 * PQ, 0);
      asm volatile(EL "@p cp.async.bulk.prefetch.L2.global [%0], 6400;\n@p cp.async.bulk.prefetch.L2.global [%1], 400;\n}"
                   ::"l"(wq + blockIdx.x * 3200), "l"((rank ? wk : wv) + (blockIdx.x >> 1) * 200) : "memory");
      {
        uint8_t* o = g_a + (size_t)(tt * 136 + 126) * 4096 + lane * 16;
#pragma unroll 1
        for (int i = 0; i < 8; i++, o += 5120) {
          st_pub128(o + j * 512, ~0u, ~0u, ~0u, ~0u);
          if (!(lane & 2)) st_pub64(o + (8 + (j >> 2)) * 512 + (j & 1) * 32 + (j & 2) * 4, ~0u, ~0u);
        }
        __syncwarp();
      }
#pragma unroll 1
      for (int i = 0; i < 2; i++) {
        mbar_sleep(sb + B_SIG + 8 * i, 0);
        if (lane == 0) asm volatile("red.release.gpu.global.add.u32 [%0], 1;" ::"l"(&g_cnt[(tt * 8 + i) * 32]) : "memory");
      }
    } else {
      {
        const int row = (tid & 63) >> 1, e = tid & 1;
        uint32_t dst = sb + SM_N24 + (row >> 3) * 384 + (row & 7) * 16;
        const __nv_bfloat16* s0 = wq + row * 640 + 80 * j + 64 + 8 * e;
        const __nv_bfloat16* s1 = (j & 1 ? wv : wk) + row * 20 + 4 * (j & 6) + 4 * e;
        mbar_sleep(sb + B_EMPTY + 8 * NS, 0);
#pragma unroll 1
        for (int i = 0; i < 20; i++, dst += 1536, s0 += 32 * 640, s1 += 32 * 20)
          asm volatile("{\n.reg .pred p;\nsetp.lt.u32 p, %4, 5;\ncp.async.cg.shared.global [%0], [%1], 16;\n@p cp.async.ca.shared.global [%2], [%3], 8;\n}"
                       ::"r"(dst + e * 128), "l"(s0), "r"(dst + 256 + e * 8), "l"(s1), "r"((j & 6) + e) : "memory");
        asm volatile("cp.async.wait_all;\nfence.proxy.async.shared::cta;" ::: "memory");
        __syncwarp();
        el_arrive(sb + B_N24);
      }
      flag_wait(&g_cnt[(lane & 15) * 8 * 32], target);
      mbar_sleep(sb + B_EMPTY + 80, 0);
      el_expect(sb + B_KVR, 16384);
      el_bulk_mc(sb + B_KVR, sb + (8 + w) * 16384 + rank * 8192, g_kv + (8 + w) * 16384 + rank * 8192);
    }
    asm volatile("setmaxnreg.inc.sync.aligned.u32 %0;" ::"n"(504 - 2 * ATTR));
    mbar_sleep(sb + B_ASFREE, 0);
    const uint32_t z = fresh_tid() * blockIdx.y;
    auto pin = [&](uint32_t v, int l) { return __shfl_sync(~0u, v + z, l); };
    ride(mp, gs, pin, z, pin(sb, 0), pin(w, 1), pin(blockIdx.x, 2), target + z);
  } else {
    const int g = lane >> 2, c = lane & 3, wi = wg * 4 + w;
    const uint32_t sd = (sb & 0x3FFFFu) >> 4;
    const uint64_t dns = ((uint64_t)(blockIdx.y + (128 >> 4)) << 32) | sd;
    const uint64_t d128 = ((uint64_t)(blockIdx.y + ((1u << 30) | (1024 >> 4))) << 32) | sd;
    const uint64_t d32 = ((uint64_t)(blockIdx.y + ((3u << 30) | (256 >> 4))) << 32) | (sd + lbo(512));
    uint32_t emp;
    asm("mapa.shared::cluster.u32 %0, %1, %2;" : "=r"(emp) : "r"(sb + B_EMPTY), "r"(rank ^ (w & 1)));
    const bool sig = (lane == 0) && (w < 2);
    uint32_t q0[6];
    {
      uint32_t a[160];
      float acc[64], rs[2];
      {
        const uint32_t lrow = sb + 65536 + wg * 8192 + (w * 16 + (lane & 15)) * 128, lsw = lane & 7, lhi = lane >> 4;
        asm volatile("setmaxnreg.inc.sync.aligned.u32 %0;" ::"n"(CONR));
        asm volatile("barrier.cluster.wait.aligned;" ::: "memory");
        float ds[16], dd[16];
#pragma unroll
        for (int i = 0; i < 16; i++) { ds[i] = 0.f; dd[i] = 0.f; }
        auto stats = [&](int kc) {
          auto sum = [&](int i, float* d) {
            asm volatile("mma.sync.aligned.m16n8k16.row.col.f32.bf16.bf16.f32 {%0,%1,%2,%3}, {%4,%5,%6,%7}, {%8,%8}, {%0,%1,%2,%3};"
                         : "+f"(d[0]), "+f"(d[1]), "+f"(d[2]), "+f"(d[3]) : "r"(a[i]), "r"(a[i + 1]), "r"(a[i + 2]), "r"(a[i + 3]), "r"(0x3f803f80u));
          };
          if (kc == 9) {
#pragma unroll
            for (int i = 0; i < 16; i += 4) sum(144 + i, ds + i);
          }
#pragma unroll
          for (int i = 16 * kc; i < 16 * kc + 16; i += 2) {
            float *d0 = dd + 4 * (i & 2), *d1 = d0 + 4;
            if (!(i & 2) && kc < 9) sum(i, ds);
            asm volatile("mma.sync.aligned.m16n8k8.row.col.f32.bf16.bf16.f32 {%0,%1,%2,%3}, {%4,%5}, {%4}, {%0,%1,%2,%3};"
                         : "+f"(d0[0]), "+f"(d0[1]), "+f"(d0[2]), "+f"(d0[3]) : "r"(a[i]), "r"(a[i + 1]));
            asm volatile("mma.sync.aligned.m16n8k8.row.col.f32.bf16.bf16.f32 {%0,%1,%2,%3}, {%4,%5}, {%5}, {%0,%1,%2,%3};"
                         : "+f"(d1[0]), "+f"(d1[1]), "+f"(d1[2]), "+f"(d1[3]) : "r"(a[i]), "r"(a[i + 1]));
          }
          if (kc < 6) mbar_arrive_if(sb + B_XFREE + 8 * kc, lane < 2);
        };
#pragma unroll
        for (int kc = 0; kc < 10; kc++) {
          if (kc == 0) asm volatile("cp.async.wait_group 1;\nbar.warp.sync 0xffffffff;" ::: "memory");
          else if (kc == 1) asm volatile("cp.async.wait_group 0;\nbar.warp.sync 0xffffffff;" ::: "memory");
          else mbar_wait(sb + B_XFULL + 8 * kc, 0);
#pragma unroll
          for (int k = 0; k < 4; k++) ldsm4(lrow + kc * 16384 + (((2 * k + lhi) ^ lsw) << 4), a + 16 * kc + 4 * k);
          if (kc > 0 && kc <= UL) stats(kc - 1);
          if (kc >= UL) stats(kc);
        }
        uint32_t mean2[2];
#pragma unroll
        for (int r = 0; r < 2; r++) {
          const float mean = ((ds[2 * r] + ds[4 + 2 * r]) + (ds[8 + 2 * r] + ds[12 + 2 * r])) * (1.f / 640.f);
          mean2[r] = pack_bf16(mean, mean);
          rs[r] = fmaf(-mean, mean, ((g & 1) ? dd[6 * r + 1] + dd[6 * r + 9] : dd[6 * r] + dd[6 * r + 8]) * (1.f / 640.f));
        }
#pragma unroll
        for (int kc = 0; kc < 10; kc++) {
          if (kc < 9) {
#pragma unroll
            for (int i = 16 * kc; i < 16 * kc + 16; i++) {
              a[i] = hsub2(a[i], mean2[i & 1]);
              asm volatile("" : "+r"(a[i])::"memory");
            }
          }
          if (kc >= 2 && kc < 6) {
            uint32_t v[4];
            const uint32_t ad = lrow + 9 * 16384 + (((2 * kc - 4 + lhi) ^ lsw) << 4);
            ldsm4(ad, v);
#pragma unroll
            for (int i = 0; i < 4; i++) v[i] = hsub2(v[i], mean2[i & 1]);
            stsm4(ad, v);
          }
          if (kc == 0) fence_regs(rs);
          if (kc == 1) {
#pragma unroll
            for (int r = 0; r < 2; r++) {
              const float var = fmaxf(__shfl_sync(~0u, rs[r], 4 * g + (g >> 1)), 0.f);
              float sq;
              asm("sqrt.approx.f32 %0, %1;" : "=f"(sq) : "f"(bf_round(bf_round(var) + 1e-5f)));
              asm("rcp.approx.f32 %0, %1;" : "=f"(rs[r]) : "f"(bf_round(sq)));
            }
            fence_regs(rs);
          }
          if (kc == 8) { fence_async_smem(); asm volatile("bar.sync %0, 128;" ::"r"(1 + wg) : "memory"); }
          if (kc == SG1 && wg == 1) asm volatile("bar.sync 4, 256;" ::: "memory");
          mbar_wait(sb + B_FULL + 8 * kc, 0);
          if (kc == SG0 && wg == 0) asm volatile("bar.arrive 4, 256;" ::: "memory");
          wg_fence();
#pragma unroll
          for (int ks = 0; ks < 4; ks++) {
            const uint64_t d = d128 + (((kc * 16384 + ks * 2048) >> 4) + lbo(8192));
            if (kc + ks == 0) wgmma_n128_rs<1, 0>(acc, a, d);
            else if (kc < 9) wgmma_n128_rs<1, 1>(acc, a + 16 * kc + 4 * ks, d);
            else wgmma_n128_ss<1, 1>(acc, d128 + (wg * (8192 >> 4) + ((SM_AS + 16384) >> 4) + 2 * ks), d);
          }
          wg_commit();
          if (kc > 0) { wg_wait<1>(); mbar_arrive_if(emp + 8 * (kc - 1), sig); }
        }
      }
#pragma unroll 1
      for (int t = 0;; t++) {
        wg_wait<0>(); fence_regs(acc);
        mbar_arrive_if(emp + 8 * 9, sig);
        uint8_t* hb = g_a + (size_t)(tt * 136 + t * 32 + j * 4) * 4096 + c * 2048 + wi * 256 + g * 16;
#pragma unroll
        for (int i = 0; i < 4; i++) {
          uint32_t v[4];
#pragma unroll
          for (int b = 0; b < 4; b++) {
            const int e = 16 * (i >> 1) + 4 * b + 2 * (i & 1);
            const float r2 = rs[i & 1] * rs[i & 1];
            v[b] = hmul2(pack_bf16(acc[e] * r2, acc[e + 1] * r2), pack_bf16(acc[32 + e], acc[33 + e]));
          }
          *(uint4*)(hb + (i >> 1) * 8192 + (i & 1) * 128) = make_uint4(v[0], v[1], v[2], v[3]);
        }
        if (t == 2) break;
        const uint64_t dt = d128 + t * blockIdx.y;
        const uint64_t da = dt + (wg * (8192 >> 4) + ((SM_AS + 16384) >> 4));
        if (t == 1) {
          float aq[32], ak[12];
          const uint64_t dn = dns + (t * blockIdx.y + (SM_N24 >> 4) + lbo(384));
          mbar_wait(sb + B_N24, 0);
          wg_fence();
#pragma unroll
          for (int k = 0; k < 40; k++) {
            if (k == 0) wgmma_n24_rs<1, 0>(ak, a, dn);
            else if (k < 36) wgmma_n24_rs<1, 1>(ak, a + 4 * k, dn + ((k * 768) >> 4));
            else wgmma_n24_ss<1, 1>(ak, da + 2 * (k & 3), dn + ((k * 768) >> 4));
          }
          wg_commit();
#pragma unroll
          for (int kc = 0; kc < 5; kc++) {
            mbar_wait(sb + B_FULL + 8 * (QS + kc), 0);
            wg_fence();
#pragma unroll
            for (int k = 8 * kc; k < 8 * kc + 8; k++) {
              const uint64_t d64 = dt + ((QS * 16384 + k * 2048) >> 4);
              if (k == 0) wgmma_n64_rs<1, 0>(aq, a, d64);
              else if (k >= 36) wgmma_n64_ss<1, 1>(aq, da + 2 * (k & 3), d64);
              else wgmma_n64_rs<1, 1>(aq, a + 4 * k, d64);
            }
            wg_commit();
            wg_wait<1>();
            if (kc) mbar_arrive_if(emp + 8 * (QS + kc - 1), sig);
            if (kc == 1) {
              mbar_arrive_if(emp + 8 * 10, sig);
              fence_regs(ak);
              if (j < 6) {
                const bool isv = j & 1;
                uint8_t* kv = g_kv + tt * 12288 + g * 16 + c * 4 + (isv ? 6144 + (j >> 1) * 128 + wi * 768 : (j >> 1) * 2048 + wi * 256);
#pragma unroll
                for (int r = 0; r < 2; r++) {
                  const bool pl = (PMASK >> (2 * wi + r)) & 1;
                  const float ks = isv ? 1.f / 256.f : pl ? 3.308722450212111e-24f : 1.8446744073709552e19f;
                  float v0 = ak[8 + 2 * r] * rs[r], v1 = ak[9 + 2 * r] * rs[r];
                  if (j >= 4 && c >= 2) {
                    v0 = c == 2 ? 1.f : isv ? 0.f : pl ? -0.5625f : -62.f;
                    v1 = isv ? 0.f : c == 2 ? 1.f : pl ? 0.875f / 128.f + 0.5625f - PSH + ((g & 1) ? PSD : 0.f) : 0.f;
                  }
                  *(uint32_t*)(kv + r * (isv ? 384 : 128)) = pack_bf16(v0 * ks, v1 * ks);
                }
              }
              __syncwarp();
              mbar_arrive_if(sb + B_SIG, lane == 0);
            }
          }
          wg_wait<0>(); fence_regs(aq);
          mbar_arrive_if(emp + 8 * (QS + 4), sig);
          const float qs = 0.32259822f * 5.421010862427522e-20f;
          uint32_t u[20];
#pragma unroll
          for (int i = 0; i < 20; i++) {
            const float* v = i < 16 ? &aq[2 * (i & 15)] : &ak[2 * (i & 3)];
            u[i] = pack_bf16(v[0] * (qs * rs[i & 1]), v[1] * (qs * rs[i & 1]));
          }
          const uint32_t sp = (c == 3) ? 0x1f801f80u : 0x2580u;
          uint8_t* qd = g_q + (size_t)blockIdx.x * (4 * 6144);
#pragma unroll
          for (int e = 0; e < 2; e++) {
            const uint32_t* b = u + 10 * e;
            uint32_t v[6];
#pragma unroll
            for (int i = 0; i < 6; i++) v[i] = __shfl_xor_sync(~0u, (i < 4 && c < 2) ? b[6 + (i & 3)] : b[4 + i], 2);
            const uint32_t e4 = c < 2 ? b[4] : sp, e5 = c < 2 ? b[5] : sp;
            *(uint4*)(qd + e * 12288 + tid * 16) = make_uint4(b[0], b[1], b[2], b[3]);
            *(uint2*)(qd + e * 12288 + 4096 + tid * 8) = make_uint2(e4, e5);
            *(uint4*)(qd + e * 12288 + 6144 + tid * 16) = make_uint4(v[0], v[1], v[2], v[3]);
            *(uint2*)(qd + e * 12288 + 10240 + tid * 8) = make_uint2(c < 2 ? v[4] : sp, c < 2 ? v[5] : sp);
            if (e == 0) { q0[0] = b[0]; q0[1] = b[1]; q0[2] = b[2]; q0[3] = b[3]; q0[4] = e4; q0[5] = e5; }
          }
        }
#pragma unroll
        for (int kc = 0; kc < 10; kc++) {
          mbar_wait(sb + B_FULL + 8 * kc, kc >= QS && kc < QS + 5 ? 1 : 1 - t);
          wg_fence();
#pragma unroll
          for (int ks = 0; ks < 4; ks++) {
            const int k = 4 * kc + ks;
            const uint64_t d = dt + (((kc * 16384 + ks * 2048) >> 4) + lbo(8192));
            if (k == 0) wgmma_n128_ss<1, 0>(acc, da, d);
            else if (k < 4) wgmma_n128_ss<1, 1>(acc, da + 2 * ks, d);
            else wgmma_n128_rs<1, 1>(acc, a + 4 * k - 16, d);
          }
          wg_commit();
          if (kc > 0) { wg_wait<1>(); mbar_arrive_if(emp + 8 * (kc - 1), sig); }
          if (kc == 1) mbar_arrive_if(sb + B_ASFREE, lane == 0 && t == 1);
        }
      }
      __syncwarp();
      mbar_arrive_if(sb + B_SIG + 8, lane == 0);
    }
    asm volatile("setmaxnreg.dec.sync.aligned.u32 %0;" ::"n"(ATTR));
    {
      const uint32_t c7f = 0x007f007fu + fresh_tid() * blockIdx.y, m1 = blockIdx.y - 1;
      const uint32_t qa = sb + SM_Q + tid * 16, qb = sb + SM_Q + 4096 + tid * 8;
      uint32_t q[8], p[32];
#pragma unroll
      for (int i = 0; i < 6; i++) q[i] = q0[i] + blockIdx.y;
      float s0[64], s1[64], o[12];
      q[6] = q0[0] & blockIdx.y; q[7] = q0[1] & blockIdx.y;
#pragma unroll
      for (int i = 0; i < 32; i++) p[i] = 0;
#pragma unroll
      for (int i = 0; i < 64; i++) { s0[i] = 0.f; s1[i] = 0.f; }
      fence_regs(q); fence_regs(p); fence_regs(s0); fence_regs(s1);
      auto row_max = [&](float (&m)[2]) {
#pragma unroll
        for (int r = 0; r < 2; r++) {
          int mm = INT_MIN, mp = INT_MIN;
#pragma unroll
          for (int b = 0; b < 16; b++) {
            int& t = is_poly(b) ? mp : mm;
            t = max(t, max(__float_as_int(s0[4 * b + 2 * r]), __float_as_int(s0[4 * b + 2 * r + 1])));
          }
          m[r] = fmaxf(__int_as_float(mm) + 62.f, (__int_as_float(mp) * 2.3611832414348226e21f) * 2.3611832414348226e21f);
          m[r] = fmaxf(m[r], __shfl_xor_sync(~0u, m[r], 1));
        }
      };
      auto row_off = [&](float (&m)[2]) {
#pragma unroll
        for (int r = 0; r < 2; r++) {
          const float off = 4116.f - fmaxf(m[r], __shfl_xor_sync(~0u, m[r], 2));
          const float hi = bf_round(off), lo = bf_round(off - hi);
          if (c == 2) q[4 + r] = pack_bf16(hi * 5.421010862427522e-20f, lo * 5.421010862427522e-20f);
          m[r] = (hi - 4096.f) + lo;
        }
      };
      auto fetch_q = [&](int hn) {
        const uint8_t* qn = g_q + (size_t)(blockIdx.x * 4 + hn) * 6144 + fresh_tid() * 8;
        asm volatile("cp.async.cg.shared.global [%0], [%1], 16;\ncp.async.ca.shared.global [%2], [%3], 8;\ncp.async.commit_group;"
                     ::"r"(qa), "l"(qn + fresh_tid() * 8), "r"(qb), "l"(qn + 4096) : "memory");
      };
      auto start = [&](const float (&m)[2]) {
#pragma unroll
        for (int i = 0; i < 64; i++) {
          const float v = m[(i >> 1) & 1];
          s0[i] = is_poly(i >> 2) ? fmaf(v * 4.235164736271502e-22f, 4.235164736271502e-22f, s0[i]) : s0[i] + v;
        }
#pragma unroll
        for (int i = 0; i < 12; i++) o[i] = 0.f;
        fence_regs(o); fence_regs(q); fence_regs(s0);
      };
      auto finish = [&](uint32_t (&v)[6], uint32_t (&bad)[2]) {
#pragma unroll
        for (int r = 0; r < 2; r++) {
          float rc, chk = 0.f;
          asm("rcp.approx.ftz.f32 %0, %1;" : "=f"(rc) : "f"(__shfl_sync(~0u, o[8 + 2 * r], (lane & ~3) | 2)));
#pragma unroll
          for (int b = 0; b < 3; b++) {
            chk += fabsf(o[4 * b + 2 * r]) + fabsf(o[4 * b + 2 * r + 1]);
            v[2 * b + r] = pack_bf16(o[4 * b + 2 * r] * rc, o[4 * b + 2 * r + 1] * rc);
          }
          bad[r] = __ballot_sync(~0u, !(chk < 8e37f));
        }
      };
      auto repair = [&](uint32_t (&v)[6], const uint32_t (&bad)[2], int h) {
        if (__builtin_expect((bad[0] | bad[1]) != 0, 0)) {
#pragma unroll 1
          for (int r = 0; r < 16; r++)
            if ((((r < 8 ? bad[0] : bad[1]) >> ((r & 7) * 4)) & 15) != 0) {
              const uint8_t* qb = g_q + (size_t)(blockIdx.x * 4 + h) * 6144 + (r >> 3) * 4;
              const int th = wi * 32 + (r & 7) * 4;
              const uint4 z = slow_row(qb + th * 16, qb + 4096 + th * 8, lane, smem, h == 3 ? 7 : 0);
              if (r == g) { v[0] = z.x; v[2] = z.y; v[4] = z.z; }
              if (r == g + 8) { v[1] = z.x; v[3] = z.y; v[5] = z.z; }
            }
        }
      };
      float m[2];
      uint32_t v[6], bad[2];
      mbar_wait(sb + B_ASFREE, 0);
      mbar_wait(sb + B_FULL, 1);
      wg_fence(); issue_qk(s0, q, dns); wg_commit();
      fetch_q(1);
#pragma unroll
      for (int i = 1; i < 4; i++) mbar_wait(sb + B_FULL + 8 * i, 1);
      wg_wait<0>(); fence_regs(s0);
      row_max(m); row_off(m); start(m);
      uint32_t msk = (~0x88808082u << 1) + blockIdx.y;
#pragma unroll 1
      for (int h = 0;; h++) {
        int it = 0;
#pragma unroll 1
        do {
          if (it) {
            mbar_wait(sb + B_KVR, 0);
            mbar_arrive_if(sb + B_KVFREE, it == 4 && lane < 2);
          }
#pragma unroll 1
          do {
            const uint64_t off = dns + it * (24576 >> 4);
            att_step<RA, RB, 0, D1>(s0, s1, p, o, q, off + (12288 >> 4), off, c7f, m1);
            asm volatile("{\n.reg .pred p;\nsetp.eq.u32 p, %8, 7;\ncp.async.wait_group 0;\n@p ld.shared.v4.u32 {%0,%1,%2,%3}, [%6];\n@p ld.shared.v2.u32 {%4,%5}, [%7];\n}"
                         : "+r"(q[0]), "+r"(q[1]), "+r"(q[2]), "+r"(q[3]), "+r"(q[4]), "+r"(q[5])
                         : "r"(qa), "r"(qb), "r"(it) : "memory");
            exp_blocks<0, D1, RC>(s1, p, c7f, m1);
            wg_wait<1>();
            att_step<RD, RE, D1, 0>(s1, s0, p, o, q, dns + ((it + 1) & 7) * (24576 >> 4), off + (12288 >> 4), c7f, m1);
            it++;
            msk >>= 1;
          } while (msk & 1);
        } while (it < 8);
        if (h == 3) break;
        fetch_q((h + 2) & 3);
        row_max(m);
        fence_regs(m);
        wg_wait<0>(); fence_regs(o);
        finish(v, bad);
        row_off(m);
        const uint32_t t = fresh_tid(), ks = h < 2 ? 8192 : 4096;
        uint8_t* ob = g_a + (size_t)(tt * 136 + 96 + (h < 2 ? h : 20)) * 4096 + ((t >> 5) * 256 + (t & 28) * 4);
        uint8_t* o1 = ob + (j * ks + (t & 2) * 1024 + (t & 1) * 8);
        uint8_t* o2 = ob + ((8 + (j >> 2)) * ks + (j & 2) * 1024 + (j & 1) * 8 + (t & 3) * 4);
        asm volatile("" : "+l"(o1), "+l"(o2));
        repair(v, bad, h);
        asm volatile("{\n.reg .pred p;\nsetp.eq.u32 p, %8, 0;\nst.global.v2.u32 [%0], {%2, %4};\nst.global.v2.u32 [%0 + 128], {%3, %5};\n"
                     "@p st.global.u32 [%1], %6;\n@p st.global.u32 [%1 + 128], %7;\n}"
                     ::"l"(o1), "l"(o2), "r"(v[0]), "r"(v[1]), "r"(v[2]), "r"(v[3]), "r"(v[4]), "r"(v[5]), "r"(t & 2) : "memory");
        __syncwarp();
        mbar_arrive_if(sb + B_SIG + 8 + 8 * h, lane == 0 && h);
        start(m);
      }
      const uint32_t t = fresh_tid();
      uint8_t* ob = g_a + (size_t)(tt * 136 + 126) * 4096 + ((t >> 5) * 5120 + (t & 31) * 16);
      asm volatile("" : "+l"(ob));
      wg_wait<0>(); fence_regs(o); fence_regs(s0);
      finish(v, bad);
      repair(v, bad, 3);
      st_pub128(ob + j * 512, v[0], v[1], v[2], v[3]);
      if (c < 2) st_pub64(ob + (8 + (j >> 2)) * 512 + (j & 1) * 32 + (j & 2) * 4, v[4], v[5]);
    }
    {
      uint32_t xr[20], a[40], gt[20];
      float d[40];
      const uint32_t t2 = fresh_tid(), lane = t2 & 31, wi = t2 >> 5;
      const uint8_t* o3 = g_a + (size_t)(tt * 136 + 126) * 4096 + wi * 5120 + lane * 16;
      const uint32_t st = sb + SM_X + wi * 2560, sl = st + (lane & 15) * 160 + (lane >> 4) * 16;
      mbar_wait(sb + B_WFULL, 0);
#pragma unroll
      for (int i = 0; i < 5; i++) lds128(sb + SM_G + i * 4096 + t2 * 16, gt + 4 * i);
#pragma unroll
      for (int i = 0; i < 10; i++)
        asm volatile("ld.shared.v4.f32 {%0,%1,%2,%3}, [%4];" : "=f"(d[4 * i]), "=f"(d[4 * i + 1]), "=f"(d[4 * i + 2]), "=f"(d[4 * i + 3]) : "r"(sb + SM_F + i * 4096 + t2 * 16) : "memory");
      uint8_t* op[5];
#pragma unroll
      for (int b = 0; b < 5; b++) {
        op[b] = out + ((size_t)(tt * 128 + wi * 16) * 1280 + 160 * j + b * 512 + lane * 16 + (lane + 32 * b) / 10 * 1120);
        asm volatile("" : "+l"(op[b]));
      }
#pragma unroll
      for (int i = 0; i < PS; i++) gt[i] = silu2(gt[i]);
      fence_regs(gt);
      if (blockIdx.y) __trap();
#pragma unroll
      for (int i = 0; i < 10; i++) ld_poll128(o3 + KS(i) * 512, a + 4 * i);
      fence_regs(gt);
#pragma unroll
      for (int i = PS; i < 20; i++) gt[i] = silu2(gt[i]);
      fence_regs(gt); fence_regs(d);
      auto again = [&](int i, uint32_t mx) {
        uint32_t* v = a + 4 * i;
        asm volatile("{\n.reg .pred p;\nsetp.eq.u32 p, %5, 0xffffffff;\n@p ld.relaxed.gpu.global.v4.u32 {%0,%1,%2,%3}, [%4];\n}"
                     : "+r"(v[0]), "+r"(v[1]), "+r"(v[2]), "+r"(v[3]) : "l"(o3 + KS(i) * 512), "r"(max(mx, v[3])) : "memory");
      };
      auto top = [&](int i) { return max(max(a[4 * i], a[4 * i + 1]), a[4 * i + 2]); };
#pragma unroll 1
      for (int n = 0; n < 1000000; n++) {
        uint32_t mx[10], miss = 0;
#pragma unroll
        for (int i = 0; i < 10; i++) {
          mx[i] = top(i);
          if (i < 5) miss = max(max(miss, mx[i]), a[4 * i + 3]);
        }
#pragma unroll
        for (int i = 5; i < 10; i++) again(i, mx[i]);
        if (!__any_sync(~0u, miss == ~0u)) break;
#pragma unroll
        for (int i = 0; i < 5; i++) again(i, mx[i]);
      }
      wg_fence();
#pragma unroll
      for (int i = 0; i < 5; i++) wgmma_n80_rs<1, 1>(d, a + 4 * i, d32 + ((SM_AS + KS(i) * 2560) >> 4));
      wg_commit();
#pragma unroll 1
      for (int n = 0; n < 1000000; n++) {
        uint32_t mx[10], miss = 0;
#pragma unroll
        for (int i = 5; i < 10; i++) {
          mx[i] = top(i);
          miss = max(max(miss, mx[i]), a[4 * i + 3]);
        }
        if (!__any_sync(~0u, miss == ~0u)) break;
#pragma unroll
        for (int i = 5; i < 10; i++) again(i, mx[i]);
      }
      wg_fence();
#pragma unroll
      for (int i = 5; i < 10; i++) wgmma_n80_rs<1, 1>(d, a + 4 * i, d32 + ((SM_AS + KS(i) * 2560) >> 4));
      wg_commit();
#pragma unroll
      for (int b = 0; b < 5; b++) ldsm4(sl + 32 * b, xr + 4 * b);
      if (blockIdx.y) __trap();
      wg_wait<0>(); fence_regs(d);
#pragma unroll
      for (int b = 0; b < 5; b++) {
        uint32_t v[4];
#pragma unroll
        for (int i = 0; i < 4; i++) {
          const int e = 8 * b + 2 * i;
          v[i] = hadd2(xr[4 * b + i], hmul2(pack_bf16(d[e], d[e + 1]), gt[4 * b + i]));
        }
        stsm4(sl + 32 * b, v);
      }
      __syncwarp();
#pragma unroll
      for (int b = 0; b < 5; b++) {
        uint32_t v[4];
        lds128(st + lane * 16 + b * 512, v);
        asm volatile("st.global.v4.u32 [%0], {%1,%2,%3,%4};" ::"l"(op[b]), "r"(v[0]), "r"(v[1]), "r"(v[2]), "r"(v[3]) : "memory");
      }
    }
  }
}

typedef CUresult (*EncodeFn)(CUtensorMap*, CUtensorMapDataType, cuuint32_t, void*, const cuuint64_t*, const cuuint64_t*,
                             const cuuint32_t*, const cuuint32_t*, CUtensorMapInterleave, CUtensorMapSwizzle,
                             CUtensorMapL2promotion, CUtensorMapFloatOOBfill);

static void enc(EncodeFn fn, CUtensorMap* m, const void* p, int rank, const cuuint64_t* dims, const cuuint64_t* strides,
                const cuuint32_t* box, CUtensorMapSwizzle sw, CUtensorMapL2promotion pr) {
  cuuint32_t es[5] = {1, 1, 1, 1, 1};
  CUresult r = fn(m, CU_TENSOR_MAP_DATA_TYPE_BFLOAT16, rank, (void*)p, dims, strides, box, es, CU_TENSOR_MAP_INTERLEAVE_NONE, sw,
                  pr, CU_TENSOR_MAP_FLOAT_OOB_FILL_NONE);
  (void)r;
}

extern "C" void kernel_launch(void* const* d_in, const int* in_sizes, int n_in, void* d_out, int out_size) {
  static EncodeFn fn = nullptr;
  static Scratch* gs = nullptr;
  if (!fn) {
    cudaGetSymbolAddress((void**)&gs, g_s);
    void* f = nullptr;
    cudaDriverEntryPointQueryResult qr;
    cudaGetDriverEntryPoint("cuTensorMapEncodeTiled", &f, cudaEnableDefault, &qr);
    fn = (EncodeFn)f;
    cudaFuncSetAttribute(fused_kernel, cudaFuncAttributeMaxDynamicSharedMemorySize, SM_TOTAL);
  }
  Maps mp;
  {
    const CUtensorMapL2promotion P256 = CU_TENSOR_MAP_L2_PROMOTION_L2_256B, P0 = CU_TENSOR_MAP_L2_PROMOTION_NONE;
    const cuuint32_t b64[2] = {64, 64}, bq[2] = {64, 128}, bxo[2] = {80, 128};
    const cuuint64_t dq[2] = {640, 640}, dg[2] = {1536, 640}, dx[2] = {640, 2048}, s640[1] = {1280}, s1536[1] = {3072};
    enc(fn, &mp.x, d_in[0], 2, dx, s640, b64, CU_TENSOR_MAP_SWIZZLE_128B, P256);
    enc(fn, &mp.q, d_in[1], 2, dq, s640, bq, CU_TENSOR_MAP_SWIZZLE_128B, P256);
    enc(fn, &mp.g, d_in[6], 2, dg, s1536, b64, CU_TENSOR_MAP_SWIZZLE_128B, P256);
    enc(fn, &mp.u, d_in[7], 2, dg, s1536, b64, CU_TENSOR_MAP_SWIZZLE_128B, P256);
    enc(fn, &mp.xo, d_in[0], 2, dx, s640, bxo, CU_TENSOR_MAP_SWIZZLE_NONE, P0);
    const cuuint64_t dd[5] = {16, 2, 4, 768, 40}, sd[4] = {1280, 10240, 2560, 32};
    const cuuint32_t bd[5] = {16, 2, 4, 2, 5};
    enc(fn, &mp.d, d_in[8], 5, dd, sd, bd, CU_TENSOR_MAP_SWIZZLE_32B, P0);
    const cuuint64_t d1[4] = {16, 80, 40, 8}, s1[3] = {1280, 32, 102400}, dp[5] = {16, 2, 2, 320, 40};
    const cuuint64_t d2[5] = {16, 4, 4, 100, 40}, s2[4] = {1280, 102400, 5120, 32};
    const cuuint32_t b1[4] = {16, 16, 5, 8}, bp[5] = {16, 2, 2, 4, 5}, b2[5] = {16, 4, 4, 1, 5};
    enc(fn, &mp.o1, d_in[4], 4, d1, s1, b1, CU_TENSOR_MAP_SWIZZLE_32B, P0);
    enc(fn, &mp.o1p, d_in[4], 5, dp, sd, bp, CU_TENSOR_MAP_SWIZZLE_32B, P0);
    enc(fn, &mp.o2, d_in[4], 5, d2, s2, b2, CU_TENSOR_MAP_SWIZZLE_32B, P0);
    const cuuint64_t da[5] = {256, 8, 1, 16 * 136, 1}, sa[4] = {512, 4096, 4096, 16 * 136 * 4096};
    const cuuint32_t ba[5] = {256, 8, 1, 1, 1};
    enc(fn, &mp.a, g_a, 5, da, sa, ba, CU_TENSOR_MAP_SWIZZLE_NONE, P0);
  }
  cudaLaunchConfig_t cfg = {};
  cfg.gridDim = dim3(128); cfg.blockDim = dim3(384); cfg.dynamicSmemBytes = SM_TOTAL; cfg.stream = cudaStreamPerThread;
  cudaLaunchAttribute at[1];
  at[0].id = cudaLaunchAttributeClusterDimension; at[0].val.clusterDim.x = 2; at[0].val.clusterDim.y = 1; at[0].val.clusterDim.z = 1;
  cfg.attrs = at; cfg.numAttrs = 1;
  cudaLaunchKernelEx(&cfg, fused_kernel, (const __nv_bfloat16*)d_in[0], gs, (uint8_t*)d_out, (const __nv_bfloat16*)d_in[1],
                     (const __nv_bfloat16*)d_in[2], (const __nv_bfloat16*)d_in[3], (const __nv_bfloat16*)d_in[4],
                     (const __nv_bfloat16*)d_in[8], mp);
}
```
